```python
import torch

def _softmax(x, axis=-1):
    return torch.softmax(x, dim=axis)
def _gelu(x):
    return torch.nn.functional.gelu(x, approximate="tanh")
def _silu(x):
    return torch.nn.functional.silu(x)
def _sigmoid(x):
    return torch.sigmoid(x)
def _layernorm(x, axis=-1, eps=1e-5):
    m = x.mean(dim=axis, keepdim=True)
    v = x.var(dim=axis, keepdim=True, unbiased=False)
    return (x - m) / torch.sqrt(v + eps)
def _scatter_add(tgt, idx, src, axis=0):
    return tgt.clone().index_add_(axis, idx, src)
def _segment_sum(src, seg, n):
    out = torch.zeros((n,) + src.shape[1:], dtype=src.dtype)
    return out.index_add_(0, seg, src)
def _pad(x, pw):
    flat = tuple(v for pair in reversed(pw) for v in pair)
    return torch.nn.functional.pad(x, flat)

kernel_name = 'concat_heads__softmax_full_mha__spectral_fnet__prompt'

def setup_inputs():

    _w = (lambda a: (lambda t: t.to(torch.bfloat16) if t.is_floating_point() else t)(torch.as_tensor(a)))
    def _A_setup():
        B, S, D = 1, 2048, 640
        return {
            "x": _w((lambda *s: torch.randn(*s, dtype=torch.bfloat16) * 0.2)(B, S, D)),
            "wqkv": _w((lambda *s: torch.randn(*s, dtype=torch.bfloat16) * 0.8)(D, 3 * D)),
            "wo": _w((lambda *s: torch.randn(*s, dtype=torch.bfloat16) * 0.2)(D, D)),
        }
    _A_in = _A_setup()

    def _B_setup():
        B, S, D = 1, 2048, 640
        ns = torch.arange(S)[:, None] * torch.arange(S)[None, :]
        nd = torch.arange(D)[:, None] * torch.arange(D)[None, :]
        Ws_re = torch.cos(-2.0 * torch.pi * ns / S).to(float)
        Ws_im = torch.sin(-2.0 * torch.pi * ns / S).to(float)
        Wd_re = torch.cos(-2.0 * torch.pi * nd / D).to(float)
        Wd_im = torch.sin(-2.0 * torch.pi * nd / D).to(float)
        return {
            "x": _w((lambda *s: torch.randn(*s, dtype=torch.bfloat16) * 0.05)(B, S, D)),
            "dft_seq_re": _w(Ws_re),
            "dft_seq_im": _w(Ws_im),
            "dft_hid_re": _w(Wd_re),
            "dft_hid_im": _w(Wd_im),
        }
    _B_in = _B_setup()

    return {
        "A_x": _A_in["x"],
        "A_wqkv": _A_in["wqkv"],
        "A_wo": _A_in["wo"],
        "B_x": _B_in["x"],
        "B_dft_seq_re": _B_in["dft_seq_re"],
        "B_dft_seq_im": _B_in["dft_seq_im"],
        "B_dft_hid_re": _B_in["dft_hid_re"],
        "B_dft_hid_im": _B_in["dft_hid_im"],
    }

def reference(A_x, A_wqkv, A_wo, B_x, B_dft_seq_re, B_dft_seq_im, B_dft_hid_re, B_dft_hid_im):
    def _A_ref(x, wqkv, wo):
        B, S, D = x.shape
        H = 32; Dh = D // H
        qkv = (lambda x, *d: x.permute(*d))((x @ wqkv).reshape(B, S, 3, H, Dh), 2, 0, 3, 1, 4)
        q, k, v = qkv[0], qkv[1], qkv[2]
        scale = Dh ** -0.5
        scores = torch.einsum("bhqd,bhkd->bhqk", q, k) * scale
        p = _softmax(scores, axis=-1)
        o = torch.einsum("bhqk,bhkd->bhqd", p, v)
        return (lambda x, *d: x.permute(*d))(o, 0, 2, 1, 3).reshape(B, S, D) @ wo

    def _B_ref(x, dft_seq_re, dft_seq_im, dft_hid_re, dft_hid_im):
        a = torch.einsum("bsd,ed->bse", x, dft_hid_re)
        b = torch.einsum("bsd,ed->bse", x, dft_hid_im)
        y = torch.einsum("ts,bse->bte", dft_seq_re, a) - torch.einsum("ts,bse->bte", dft_seq_im, b)
        return y

    a = _A_ref(A_x, A_wqkv, A_wo)
    b = _B_ref(B_x, B_dft_seq_re, B_dft_seq_im, B_dft_hid_re, B_dft_hid_im)
    return torch.concatenate([a, b], axis=-1)
```

```cpp
#include <cuda_runtime.h>
#include <cuda.h>
#include <cuda_bf16.h>
#include <stdint.h>

namespace {

constexpr int S_ = 2048, D_ = 640;
constexpr int HP_BYTES = 16 * 6144;
__device__ __align__(1024) unsigned char g_qkv[96 * HP_BYTES];
#define CTA ((blockIdx.x & 0x70) | (blockIdx.x & 1) << 3 | (blockIdx.x >> 1 & 7))
__device__ __forceinline__ unsigned char* qkv_block(int part, int rb) {
  return g_qkv + (part < 32 ? part * 16 + rb : part < 64 ? part * 32 - 512 + 2 * rb : part * 32 - 1535 + 2 * ((rb + 1) & 15)) * 6144;
}
__device__ __align__(1024) unsigned char g_ab[8 * 256 * 2560];
__device__ __align__(1024) unsigned char g_o[16 * 80 * 2048];
__device__ __align__(1024) uint4 g_o3[16 * 20 * 128];
__device__ __align__(1024) uint4 g_x[128 * 10 * 128];
constexpr int C_QKV = 0, C_F1 = 32, C_F2 = 160, C_O = 288, C_DONE = 416, C_Q0 = 448, C_NUM = 640;
__device__ __align__(128) unsigned int g_cnt[C_NUM];

constexpr uint32_t KBIAS = 0x1B561F7Cu;
template<int TB> __device__ __forceinline__ void wgmma_rs_n24(float (&d)[12], uint32_t a0, uint32_t a1, uint32_t a2, uint32_t a3, uint64_t db, int scale_d) {
  asm volatile("{\n.reg .pred p;\nsetp.ne.b32 p, %17, 0;\n"
    "wgmma.mma_async.sync.aligned.m64n24k16.f32.bf16.bf16 {%0,%1,%2,%3,%4,%5,%6,%7,%8,%9,%10,%11}, {%12,%13,%14,%15}, %16, p, 1, 1, %18;\n}\n"
    : "+f"(d[0]),"+f"(d[1]),"+f"(d[2]),"+f"(d[3]),"+f"(d[4]),"+f"(d[5]),"+f"(d[6]),"+f"(d[7]),"+f"(d[8]),"+f"(d[9]),"+f"(d[10]),"+f"(d[11])
    : "r"(a0), "r"(a1), "r"(a2), "r"(a3), "l"(db), "r"(scale_d), "n"(TB));
}
template<int TB> __device__ __forceinline__ void wgmma_rs_n64(float (&d)[32], uint32_t a0, uint32_t a1, uint32_t a2, uint32_t a3, uint64_t db, int scale_d) {
  asm volatile("{\n.reg .pred p;\nsetp.ne.b32 p, %37, 0;\n"
    "wgmma.mma_async.sync.aligned.m64n64k16.f32.bf16.bf16 {%0,%1,%2,%3,%4,%5,%6,%7,%8,%9,%10,%11,%12,%13,%14,%15,%16,%17,%18,%19,%20,%21,%22,%23,%24,%25,%26,%27,%28,%29,%30,%31}, {%32,%33,%34,%35}, %36, p, 1, 1, %38;\n}\n"
    : "+f"(d[0]),"+f"(d[1]),"+f"(d[2]),"+f"(d[3]),"+f"(d[4]),"+f"(d[5]),"+f"(d[6]),"+f"(d[7]),"+f"(d[8]),"+f"(d[9]),"+f"(d[10]),"+f"(d[11]),"+f"(d[12]),"+f"(d[13]),"+f"(d[14]),"+f"(d[15]),"+f"(d[16]),"+f"(d[17]),"+f"(d[18]),"+f"(d[19]),"+f"(d[20]),"+f"(d[21]),"+f"(d[22]),"+f"(d[23]),"+f"(d[24]),"+f"(d[25]),"+f"(d[26]),"+f"(d[27]),"+f"(d[28]),"+f"(d[29]),"+f"(d[30]),"+f"(d[31])
    : "r"(a0), "r"(a1), "r"(a2), "r"(a3), "l"(db), "r"(scale_d), "n"(TB));
}
template<int TB> __device__ __forceinline__ void wgmma_rs_n80(float (&d)[40], uint32_t a0, uint32_t a1, uint32_t a2, uint32_t a3, uint64_t db, int scale_d) {
  asm volatile("{\n.reg .pred p;\nsetp.ne.b32 p, %45, 0;\n"
    "wgmma.mma_async.sync.aligned.m64n80k16.f32.bf16.bf16 {%0,%1,%2,%3,%4,%5,%6,%7,%8,%9,%10,%11,%12,%13,%14,%15,%16,%17,%18,%19,%20,%21,%22,%23,%24,%25,%26,%27,%28,%29,%30,%31,%32,%33,%34,%35,%36,%37,%38,%39}, {%40,%41,%42,%43}, %44, p, 1, 1, %46;\n}\n"
    : "+f"(d[0]),"+f"(d[1]),"+f"(d[2]),"+f"(d[3]),"+f"(d[4]),"+f"(d[5]),"+f"(d[6]),"+f"(d[7]),"+f"(d[8]),"+f"(d[9]),"+f"(d[10]),"+f"(d[11]),"+f"(d[12]),"+f"(d[13]),"+f"(d[14]),"+f"(d[15]),"+f"(d[16]),"+f"(d[17]),"+f"(d[18]),"+f"(d[19]),"+f"(d[20]),"+f"(d[21]),"+f"(d[22]),"+f"(d[23]),"+f"(d[24]),"+f"(d[25]),"+f"(d[26]),"+f"(d[27]),"+f"(d[28]),"+f"(d[29]),"+f"(d[30]),"+f"(d[31]),"+f"(d[32]),"+f"(d[33]),"+f"(d[34]),"+f"(d[35]),"+f"(d[36]),"+f"(d[37]),"+f"(d[38]),"+f"(d[39])
    : "r"(a0), "r"(a1), "r"(a2), "r"(a3), "l"(db), "r"(scale_d), "n"(TB));
}
template<int TA, int TB, int SA = 1> __device__ __forceinline__ void wgmma_ss_n80(float (&d)[40], uint64_t da, uint64_t db, int scale_d) {
  asm volatile("{\n.reg .pred p;\nsetp.ne.b32 p, %42, 0;\n"
    "wgmma.mma_async.sync.aligned.m64n80k16.f32.bf16.bf16 {%0,%1,%2,%3,%4,%5,%6,%7,%8,%9,%10,%11,%12,%13,%14,%15,%16,%17,%18,%19,%20,%21,%22,%23,%24,%25,%26,%27,%28,%29,%30,%31,%32,%33,%34,%35,%36,%37,%38,%39}, %40, %41, p, %45, 1, %43, %44;\n}\n"
    : "+f"(d[0]),"+f"(d[1]),"+f"(d[2]),"+f"(d[3]),"+f"(d[4]),"+f"(d[5]),"+f"(d[6]),"+f"(d[7]),"+f"(d[8]),"+f"(d[9]),"+f"(d[10]),"+f"(d[11]),"+f"(d[12]),"+f"(d[13]),"+f"(d[14]),"+f"(d[15]),"+f"(d[16]),"+f"(d[17]),"+f"(d[18]),"+f"(d[19]),"+f"(d[20]),"+f"(d[21]),"+f"(d[22]),"+f"(d[23]),"+f"(d[24]),"+f"(d[25]),"+f"(d[26]),"+f"(d[27]),"+f"(d[28]),"+f"(d[29]),"+f"(d[30]),"+f"(d[31]),"+f"(d[32]),"+f"(d[33]),"+f"(d[34]),"+f"(d[35]),"+f"(d[36]),"+f"(d[37]),"+f"(d[38]),"+f"(d[39])
    : "l"(da), "l"(db), "r"(scale_d), "n"(TA), "n"(TB), "n"(SA));
}
template<int TA, int TB, int SA = 1> __device__ __forceinline__ void wgmma_ss_n112(float (&d)[56], uint64_t da, uint64_t db, int scale_d) {
  asm volatile("{\n.reg .pred p;\nsetp.ne.b32 p, %58, 0;\n"
    "wgmma.mma_async.sync.aligned.m64n112k16.f32.bf16.bf16 {%0,%1,%2,%3,%4,%5,%6,%7,%8,%9,%10,%11,%12,%13,%14,%15,%16,%17,%18,%19,%20,%21,%22,%23,%24,%25,%26,%27,%28,%29,%30,%31,%32,%33,%34,%35,%36,%37,%38,%39,%40,%41,%42,%43,%44,%45,%46,%47,%48,%49,%50,%51,%52,%53,%54,%55}, %56, %57, p, %61, 1, %59, %60;\n}\n"
    : "+f"(d[0]),"+f"(d[1]),"+f"(d[2]),"+f"(d[3]),"+f"(d[4]),"+f"(d[5]),"+f"(d[6]),"+f"(d[7]),"+f"(d[8]),"+f"(d[9]),"+f"(d[10]),"+f"(d[11]),"+f"(d[12]),"+f"(d[13]),"+f"(d[14]),"+f"(d[15]),"+f"(d[16]),"+f"(d[17]),"+f"(d[18]),"+f"(d[19]),"+f"(d[20]),"+f"(d[21]),"+f"(d[22]),"+f"(d[23]),"+f"(d[24]),"+f"(d[25]),"+f"(d[26]),"+f"(d[27]),"+f"(d[28]),"+f"(d[29]),"+f"(d[30]),"+f"(d[31]),"+f"(d[32]),"+f"(d[33]),"+f"(d[34]),"+f"(d[35]),"+f"(d[36]),"+f"(d[37]),"+f"(d[38]),"+f"(d[39]),"+f"(d[40]),"+f"(d[41]),"+f"(d[42]),"+f"(d[43]),"+f"(d[44]),"+f"(d[45]),"+f"(d[46]),"+f"(d[47]),"+f"(d[48]),"+f"(d[49]),"+f"(d[50]),"+f"(d[51]),"+f"(d[52]),"+f"(d[53]),"+f"(d[54]),"+f"(d[55])
    : "l"(da), "l"(db), "r"(scale_d), "n"(TA), "n"(TB), "n"(SA));
}
template<int TA, int TB, int SA = 1> __device__ __forceinline__ void wgmma_ss_n128(float (&d)[64], uint64_t da, uint64_t db, int scale_d) {
  asm volatile("{\n.reg .pred p;\nsetp.ne.b32 p, %66, 0;\n"
    "wgmma.mma_async.sync.aligned.m64n128k16.f32.bf16.bf16 {%0,%1,%2,%3,%4,%5,%6,%7,%8,%9,%10,%11,%12,%13,%14,%15,%16,%17,%18,%19,%20,%21,%22,%23,%24,%25,%26,%27,%28,%29,%30,%31,%32,%33,%34,%35,%36,%37,%38,%39,%40,%41,%42,%43,%44,%45,%46,%47,%48,%49,%50,%51,%52,%53,%54,%55,%56,%57,%58,%59,%60,%61,%62,%63}, %64, %65, p, %69, 1, %67, %68;\n}\n"
    : "+f"(d[0]),"+f"(d[1]),"+f"(d[2]),"+f"(d[3]),"+f"(d[4]),"+f"(d[5]),"+f"(d[6]),"+f"(d[7]),"+f"(d[8]),"+f"(d[9]),"+f"(d[10]),"+f"(d[11]),"+f"(d[12]),"+f"(d[13]),"+f"(d[14]),"+f"(d[15]),"+f"(d[16]),"+f"(d[17]),"+f"(d[18]),"+f"(d[19]),"+f"(d[20]),"+f"(d[21]),"+f"(d[22]),"+f"(d[23]),"+f"(d[24]),"+f"(d[25]),"+f"(d[26]),"+f"(d[27]),"+f"(d[28]),"+f"(d[29]),"+f"(d[30]),"+f"(d[31]),"+f"(d[32]),"+f"(d[33]),"+f"(d[34]),"+f"(d[35]),"+f"(d[36]),"+f"(d[37]),"+f"(d[38]),"+f"(d[39]),"+f"(d[40]),"+f"(d[41]),"+f"(d[42]),"+f"(d[43]),"+f"(d[44]),"+f"(d[45]),"+f"(d[46]),"+f"(d[47]),"+f"(d[48]),"+f"(d[49]),"+f"(d[50]),"+f"(d[51]),"+f"(d[52]),"+f"(d[53]),"+f"(d[54]),"+f"(d[55]),"+f"(d[56]),"+f"(d[57]),"+f"(d[58]),"+f"(d[59]),"+f"(d[60]),"+f"(d[61]),"+f"(d[62]),"+f"(d[63])
    : "l"(da), "l"(db), "r"(scale_d), "n"(TA), "n"(TB), "n"(SA));
}
template<int TA, int TB, int SA = 1> __device__ __forceinline__ void wgmma_ss_n160(float (&d)[80], uint64_t da, uint64_t db, int scale_d) {
  asm volatile("{\n.reg .pred p;\nsetp.ne.b32 p, %82, 0;\n"
    "wgmma.mma_async.sync.aligned.m64n160k16.f32.bf16.bf16 {%0,%1,%2,%3,%4,%5,%6,%7,%8,%9,%10,%11,%12,%13,%14,%15,%16,%17,%18,%19,%20,%21,%22,%23,%24,%25,%26,%27,%28,%29,%30,%31,%32,%33,%34,%35,%36,%37,%38,%39,%40,%41,%42,%43,%44,%45,%46,%47,%48,%49,%50,%51,%52,%53,%54,%55,%56,%57,%58,%59,%60,%61,%62,%63,%64,%65,%66,%67,%68,%69,%70,%71,%72,%73,%74,%75,%76,%77,%78,%79}, %80, %81, p, %85, 1, %83, %84;\n}\n"
    : "+f"(d[0]),"+f"(d[1]),"+f"(d[2]),"+f"(d[3]),"+f"(d[4]),"+f"(d[5]),"+f"(d[6]),"+f"(d[7]),"+f"(d[8]),"+f"(d[9]),"+f"(d[10]),"+f"(d[11]),"+f"(d[12]),"+f"(d[13]),"+f"(d[14]),"+f"(d[15]),"+f"(d[16]),"+f"(d[17]),"+f"(d[18]),"+f"(d[19]),"+f"(d[20]),"+f"(d[21]),"+f"(d[22]),"+f"(d[23]),"+f"(d[24]),"+f"(d[25]),"+f"(d[26]),"+f"(d[27]),"+f"(d[28]),"+f"(d[29]),"+f"(d[30]),"+f"(d[31]),"+f"(d[32]),"+f"(d[33]),"+f"(d[34]),"+f"(d[35]),"+f"(d[36]),"+f"(d[37]),"+f"(d[38]),"+f"(d[39]),"+f"(d[40]),"+f"(d[41]),"+f"(d[42]),"+f"(d[43]),"+f"(d[44]),"+f"(d[45]),"+f"(d[46]),"+f"(d[47]),"+f"(d[48]),"+f"(d[49]),"+f"(d[50]),"+f"(d[51]),"+f"(d[52]),"+f"(d[53]),"+f"(d[54]),"+f"(d[55]),"+f"(d[56]),"+f"(d[57]),"+f"(d[58]),"+f"(d[59]),"+f"(d[60]),"+f"(d[61]),"+f"(d[62]),"+f"(d[63]),"+f"(d[64]),"+f"(d[65]),"+f"(d[66]),"+f"(d[67]),"+f"(d[68]),"+f"(d[69]),"+f"(d[70]),"+f"(d[71]),"+f"(d[72]),"+f"(d[73]),"+f"(d[74]),"+f"(d[75]),"+f"(d[76]),"+f"(d[77]),"+f"(d[78]),"+f"(d[79])
    : "l"(da), "l"(db), "r"(scale_d), "n"(TA), "n"(TB), "n"(SA));
}

#define WG_FENCE() asm volatile("wgmma.fence.sync.aligned;" ::: "memory")
#define WG_COMMIT() asm volatile("wgmma.commit_group.sync.aligned;" ::: "memory")
#define WG_WAIT0() asm volatile("wgmma.wait_group.sync.aligned 0;" ::: "memory")
#define WG_DRAIN() do { WG_COMMIT(); WG_WAIT0(); WG_FENCE(); } while (0)

__device__ __forceinline__ uint64_t desc2(uint32_t lo, uint32_t hi) { return ((uint64_t)hi << 32) | lo; }
__device__ __forceinline__ uint32_t dlo(uint32_t addr, uint32_t lbo) { return ((addr & 0x3FFFF) >> 4) | ((lbo >> 4) << 16); }
constexpr uint32_t HI_SW64 = (512 >> 4) | (2u << 30);
constexpr uint32_t HI_SW128 = (1024 >> 4) | (1u << 30);

__device__ __forceinline__ void mbar_init(uint32_t a, int c) { asm volatile("mbarrier.init.shared::cta.b64 [%0], %1;" ::"r"(a), "r"(c)); }
#define ONE(x) "{.reg .pred p; elect.sync _|p, 0xffffffff;\n @p " x "}"
__device__ __forceinline__ void mbar_arrive_elect(uint32_t a) { asm volatile(ONE("mbarrier.arrive.shared::cta.b64 _, [%0];") ::"r"(a) : "memory"); }
__device__ __forceinline__ void mbar_expect(uint32_t a, uint32_t b) {
  asm volatile(ONE("mbarrier.arrive.expect_tx.shared::cta.b64 _, [%0], %1;") ::"r"(a), "r"(b) : "memory");
}
template <int LIMIT = 4000000> __device__ __forceinline__ void mbar_wait(uint32_t a, uint32_t ph) {
  uint32_t ok; int n = 0;
  do {
    asm volatile("{.reg .pred p; mbarrier.try_wait.parity.shared::cta.b64 p, [%1], %2; selp.u32 %0,1,0,p;}" : "=r"(ok) : "r"(a), "r"(ph) : "memory");
    if (++n > LIMIT) break;
  } while (!ok);
}
__device__ __forceinline__ uint32_t mbar_test(uint32_t a, uint32_t ph) {
  uint32_t ok;
  asm volatile("{.reg .pred p; mbarrier.test_wait.parity.shared::cta.b64 p, [%1], %2; selp.u32 %0,1,0,p;}" : "=r"(ok) : "r"(a), "r"(ph) : "memory");
  return ok;
}
__device__ __forceinline__ void cnt_add(int idx) { asm volatile(ONE("red.relaxed.gpu.global.add.u32 [%0], 1;") ::"l"(g_cnt + idx) : "memory"); }
__device__ __forceinline__ void fence_async() { asm volatile("fence.proxy.async.global;" ::: "memory"); }
__device__ __forceinline__ void bulk(uint32_t dst, const void* src, uint32_t bytes, uint32_t bar) {
  asm volatile(ONE("cp.async.bulk.shared::cluster.global.mbarrier::complete_tx::bytes [%0], [%1], %2, [%3];") ::"r"(dst), "l"(src), "r"(bytes), "r"(bar) : "memory");
}
__device__ __forceinline__ void bulk_store(void* dst, uint32_t src, uint32_t bytes) {
  asm volatile(ONE("cp.async.bulk.global.shared::cta.bulk_group [%0], [%1], %2;") ::"l"(dst), "r"(src), "r"(bytes) : "memory");
}
__device__ __forceinline__ void fence_smem() { asm volatile("fence.proxy.async.shared::cta;" ::: "memory"); }
__device__ __forceinline__ void stage_done(uint32_t bar) {
  __syncwarp();
  mbar_arrive_elect(bar);
}
template <bool FENCE = true> __device__ __forceinline__ uint32_t poll_flags(const unsigned int* p, uint32_t target, uint32_t need) {
  uint32_t v, ready; int n = 0;
  do {
    asm volatile("ld.relaxed.gpu.global.u32 %0, [%1];" : "=r"(v) : "l"(p) : "memory");
    ready = __ballot_sync(0xffffffffu, v >= target);
  } while ((ready & need) != need && ++n < 1000000);
  if (FENCE) fence_async();
  return ready;
}
__device__ __forceinline__ void tma2(uint32_t dst, const CUtensorMap* m, int c0, int c1, uint32_t bar) {
  asm volatile(ONE("cp.async.bulk.tensor.2d.shared::cluster.global.mbarrier::complete_tx::bytes [%0], [%1, {%3,%4}], [%2];") ::"r"(dst), "l"(m), "r"(bar), "r"(c0), "r"(c1) : "memory");
}
__device__ __forceinline__ void tma3(uint32_t dst, const CUtensorMap* m, int c0, int c1, int c2, uint32_t bar) {
  asm volatile(ONE("cp.async.bulk.tensor.3d.shared::cluster.global.mbarrier::complete_tx::bytes [%0], [%1, {%3,%4,%5}], [%2];") ::"r"(dst), "l"(m), "r"(bar), "r"(c0), "r"(c1), "r"(c2) : "memory");
}
__device__ __forceinline__ float ex2(float x) { float y; asm("ex2.approx.ftz.f32 %0, %1;" : "=f"(y) : "f"(x)); return y; }
__device__ __forceinline__ float rcp(float x) { float y; asm("rcp.approx.ftz.f32 %0, %1;" : "=f"(y) : "f"(x)); return y; }
__device__ __forceinline__ uint32_t pack(float a, float b) { uint32_t r; asm("cvt.rn.bf16x2.f32 %0, %1, %2;" : "=r"(r) : "f"(b), "f"(a)); return r; }
__device__ __forceinline__ uint32_t lds32(uint32_t a) { uint32_t v; asm volatile("ld.shared.u32 %0, [%1];" : "=r"(v) : "r"(a) : "memory"); return v; }
__device__ __forceinline__ void sts32(uint32_t a, uint32_t v) { asm volatile("st.shared.u32 [%0], %1;" ::"r"(a), "r"(v) : "memory"); }
__device__ __forceinline__ void sts128(uint32_t p, uint32_t a, uint32_t b, uint32_t c, uint32_t d) {
  asm volatile("st.shared.v4.u32 [%0], {%1,%2,%3,%4};" ::"r"(p), "r"(a), "r"(b), "r"(c), "r"(d) : "memory");
}
__device__ __forceinline__ void stg32(void* p, uint32_t v) { asm volatile("st.global.u32 [%0], %1;" ::"l"(p), "r"(v) : "memory"); }
__device__ __forceinline__ void stg128(void* p, uint32_t a, uint32_t b, uint32_t c, uint32_t d) {
  asm volatile("st.global.v4.u32 [%0], {%1,%2,%3,%4};" ::"l"(p), "r"(a), "r"(b), "r"(c), "r"(d) : "memory");
}
template <int N> __device__ __forceinline__ void fence_regs(float (&d)[N]) {
#pragma unroll
  for (int i = 0; i < N; i++) asm volatile("" : "+f"(d[i])::"memory");
}
template <int N> __device__ __forceinline__ void fence_regs(uint32_t (&d)[N]) {
#pragma unroll
  for (int i = 0; i < N; i++) asm volatile("" : "+r"(d[i])::"memory");
}

constexpr uint32_t QS_BYTES = 49152, G_BYTES = 36864, KV_BYTES = 12288;
constexpr uint32_t OFF_KV = 4 * G_BYTES, OFF_Q = 4 * QS_BYTES, OFF_BAR = OFF_Q + 30720;
constexpr uint32_t B_QFULL = 0, B_QEMPTY = 32, B_GFULL = 64, B_GEMPTY = 96, B_KVFULL = 128, B_KVEMPTY = 160, B_O = 192, B_Q = 224, B_ZERO = 232, B_ST = 240, B_STFREE = 248, B_Q2 = 256, B_PFULL = 264, B_PEMPTY = 288, B_ST2 = 312, B_CONST = 320, B_F1 = 328, B_F1FREE = 336, B_X = 344, B_X2 = 352, B_QF2 = 416, B_F1A = 360;
constexpr uint32_t OFF_X = G_BYTES;
constexpr uint32_t P_BYTES = 35840;
constexpr uint32_t SMEM_BYTES = OFF_BAR + 512 + 1024;

template <int B0, int NB, bool FIRST> __device__ __forceinline__ void store_qkv(const float (&d)[NB * 4], int j, uint32_t base, int lane) {
  const int c = lane & 3;
#pragma unroll
  for (int b = 0; b < NB; b++) {
    const int gb = B0 + b, pr = gb / 5, sub = gb % 5;
    const int ty = (6 * j + pr) >> 4;
#pragma unroll
    for (int hh = 0; hh < 2; hh++) {
      const bool sw = hh;
      const float sc = ty == 0 ? 0.32259622f * 0x1p-71f : ty == 2 ? 1.0f : sw ? 0x1p-71f : 0x1p71f;
      uint32_t v = pack(d[4 * b + 2 * hh] * sc, d[4 * b + 2 * hh + 1] * sc);
      const uint32_t p = base + (FIRST ? OFF_Q + 6144 + pr * 3072 : 2 * pr * 6144) + hh * 384;
      const bool first = !(pr & 1);
      if (sub < 2) { if (first == FIRST) sts32(p + sub * 128, v); }
      else if (sub > 2) { if (!FIRST) sts32(p + 6144 + (sub - 3) * 128, v); }
      else {
        const uint32_t pad = (c & 1) ? (ty == 0 ? 0x1C001C00u : (ty == 1 && sw) ? KBIAS : 0u) : (ty == 0 ? 0u : ty == 2 ? 0x3F80u : sw ? 0x1C00u : 0x6300u);
        if (first == FIRST) sts32(p + 256, c < 2 ? v : pad);
        if (!FIRST) sts32(p + 6144 + 256, c >= 2 ? v : pad);
      }
    }
  }
}

__device__ __forceinline__ uint32_t ex2_pair(float u0, float u1, uint32_t half) {
  uint32_t w, z, r;
  asm("cvt.pack.sat.s16.s32 %0, %1, %2;" : "=r"(w) : "r"(__float_as_uint(u1)), "r"(__float_as_uint(u0)));
  asm("lop3.b32 %0, %1, 0x007F007F, %2, 0xEA;" : "=r"(z) : "r"(w), "r"(half));
  asm("fma.rn.bf16x2 %0, %1, %2, %3;" : "=r"(r) : "r"(w), "r"(z), "r"(w & 0xFF80FF80u));
  return r;
}
template <int MASK> __device__ __forceinline__ void softmax_tile(const float (&S)[32], uint32_t (&P)[16], uint32_t half) {
#pragma unroll
  for (int u = 0; u < 16; u++)
    if ((MASK >> (u >> 1)) & 1) P[u] = (u & 2) ? ex2_pair(S[2 * u], S[2 * u + 1], half) : pack(ex2(S[2 * u]), ex2(S[2 * u + 1]));
}
template <int MASK> __device__ __forceinline__ void touch(float (&S)[32], uint32_t zero) {
#pragma unroll
  for (int i = 0; i < 32; i++)
    if (((MASK >> (i >> 2)) & 1) && ((i & 1) || !(i & 4))) asm volatile("or.b32 %0, %0, %1;" : "+f"(S[i]) : "r"(zero));
}
__device__ __forceinline__ void pin(const uint32_t (&P)[16], uint32_t a, uint32_t ok) {
  asm volatile("{.reg .pred p; setp.eq.u32 p, %5, 0; @p st.shared.v4.u32 [%0], {%1,%2,%3,%4};}" ::"r"(a), "r"(P[8]), "r"(P[9]), "r"(P[10]), "r"(P[11]), "r"(ok) : "memory");
}
__device__ __forceinline__ void att_issue(float (&S)[32], const uint32_t (&P)[16], float (&O)[12], const uint32_t (&qa)[8], const uint64_t* dk, const uint64_t* dv) {
  wgmma_rs_n24<1>(O, P[0], P[1], P[2], P[3], dv[0], 1);
  wgmma_rs_n64<0>(S, qa[0], qa[1], qa[2], qa[3], dk[0], 0);
  wgmma_rs_n24<1>(O, P[4], P[5], P[6], P[7], dv[1], 1);
  wgmma_rs_n64<0>(S, qa[4], qa[5], qa[6], qa[7], dk[1], 1);
  wgmma_rs_n24<1>(O, P[8], P[9], P[10], P[11], dv[2], 1);
  wgmma_rs_n24<1>(O, P[12], P[13], P[14], P[15], dv[3], 1);
  WG_COMMIT();
}
__device__ __forceinline__ uint32_t tid_now() { uint32_t t; asm volatile("mov.u32 %0, %%tid.x;" : "=r"(t)); return t; }
__device__ __forceinline__ void load_q(uint32_t (&qa)[8], uint32_t a) {
  qa[0] = lds32(a); qa[1] = lds32(a + 384); qa[2] = lds32(a + 128); qa[3] = lds32(a + 512);
  qa[4] = lds32(a + 256); qa[5] = lds32(a + 640);
}
__device__ __forceinline__ uint32_t row_shift(float m0, float m1) {
  uint32_t m = pack(m0, m1);
  asm("max.bf16x2 %0, %0, %1;" : "+r"(m) : "r"(__shfl_xor_sync(0xffffffffu, m, 1)));
  asm("max.bf16x2 %0, %0, %1;" : "+r"(m) : "r"(__shfl_xor_sync(0xffffffffu, m, 2)));
  asm("fma.rn.bf16x2 %0, %0, %1, %2;" : "+r"(m) : "r"(0x9C009C00u), "r"(0x9F109F10u));
  return m;
}
__device__ __forceinline__ bool norm_o(const float (&O)[12], uint32_t (&v)[6], int src) {
  const float l0 = __shfl_sync(0xffffffffu, O[8], src), l1 = __shfl_sync(0xffffffffu, O[10], src);
  const float r0 = rcp(l0), r1 = rcp(l1);
  uint32_t z = 0;
#pragma unroll
  for (int i = 0; i < 6; i++) {
    v[i] = pack(O[2 * i] * (i & 1 ? r1 : r0), O[2 * i + 1] * (i & 1 ? r1 : r0));
    asm("max.u16x2 %0, %0, %1;" : "+r"(z) : "r"(v[i] & 0x7FFF7FFFu));
  }
  const bool bad = ((z + 0x00800080u) & 0x80008000u) || max(__float_as_uint(l0) - (27u << 23), __float_as_uint(l1) - (27u << 23)) >= (220u << 23);
  return __any_sync(0xffffffffu, bad);
}
__device__ __forceinline__ void store_o(const uint32_t (&v)[6], int p, uint32_t t) {
  const uint32_t odd = p & 1, k0 = 20 * (CTA & 7) + 2 * (t & 3), ka = k0 + 4 * odd, kc = k0 + 16 - 20 * odd;
  const uint32_t row = (t >> 5) * 256 + (t & 28) * 4;
  unsigned char* op = g_o + ((CTA >> 3) * 80 + p * 20) * 2048;
  unsigned char* p0 = op + (row + (ka >> 3) * 2048 + (ka & 7) * 2);
  stg32(p0, v[0]); stg32(p0 + 128, v[1]); stg32(p0 + 2048, v[2]); stg32(p0 + 2048 + 128, v[3]);
  unsigned char* p2 = op + (row + (kc >> 3) * 2048 + (kc & 7) * 2);
  asm volatile("{.reg .pred p; setp.eq.u32 p, %3, %4; @p st.global.u32 [%0], %1; @p st.global.u32 [%0+128], %2;}" ::"l"(p2), "r"(v[4]), "r"(v[5]), "r"(t & 2), "r"(odd * 2) : "memory");
}
__device__ __forceinline__ void store_o3(const uint32_t (&v)[6], uint32_t t) {
  const int j = CTA & 7;
  const uint32_t a0 = v[0], a1 = v[1], b0 = v[2], b1 = v[3], c0 = v[4], c1 = v[5];
  const bool hi = t & 2, sh = hi && !(j & 1);
  uint4* p = g_o3 + (((CTA >> 2) * 2 + (t >> 7)) * 5) * 128 + ((t & 127) ^ (j & 1 ? 0 : 2));
  stg128(p + (j & 3) * 128, sh ? c0 : a0, sh ? c1 : a1, sh ? a0 : b0, sh ? a1 : b1);
  if (hi) asm volatile("st.global.v2.u32 [%0], {%1,%2};" ::"l"((unsigned char*)(p + 512) + (j & 2) * 4), "r"(sh ? b0 : c0), "r"(sh ? b1 : c1) : "memory");
}
__device__ __forceinline__ void load_o3(uint32_t (&a)[40], const uint4* src) {
#pragma unroll
  for (int i = 0; i < 10; i++)
    asm volatile("ld.relaxed.gpu.global.v4.u32 {%0,%1,%2,%3}, [%4];" : "=r"(a[4 * i]), "=r"(a[4 * i + 1]), "=r"(a[4 * i + 2]), "=r"(a[4 * i + 3]) : "l"(src + i * 128) : "memory");
}
__device__ __forceinline__ void check_o3(uint32_t (&a)[40], const uint4* src) {
#pragma unroll 1
  for (int n = 0; n < 400000; n++) {
    uint32_t m = 0;
#pragma unroll
    for (int i = 0; i < 40; i++) m = max(m, a[i]);
    if (!__any_sync(0xffffffffu, m == 0xFFFFFFFFu)) break;
    if (n > 4) __nanosleep(500);
#pragma unroll
      for (int i = 0; i < 10; i++)
        asm volatile("{.reg .pred p; setp.eq.u32 p, %5, 0xFFFFFFFF; @p ld.relaxed.gpu.global.v4.u32 {%0,%1,%2,%3}, [%4];}"
                     : "+r"(a[4 * i]), "+r"(a[4 * i + 1]), "+r"(a[4 * i + 2]), "+r"(a[4 * i + 3])
                     : "l"(src + i * 128), "r"(max(max(a[4 * i], a[4 * i + 1]), max(a[4 * i + 2], a[4 * i + 3]))) : "memory");
  }
}
__device__ __forceinline__ void mma_o3(float (&e0)[40], float (&e1)[40], const uint32_t (&a)[40], uint32_t b) {
  WG_FENCE();
#pragma unroll
  for (int k = 0; k < 5; k++) {
    const uint64_t db = k == 4 ? desc2(b + 64, (2560 >> 4) | (2u << 30)) : desc2(b + 32 * ((5 * k + 1) >> 1), HI_SW64);
    wgmma_rs_n80<1>(e0, a[4 * k], a[4 * k + 1], a[4 * k + 2], a[4 * k + 3], db, 1);
    wgmma_rs_n80<1>(e1, a[20 + 4 * k], a[21 + 4 * k], a[22 + 4 * k], a[23 + 4 * k], db, 1);
  }
  WG_COMMIT();
}
__device__ __forceinline__ void mma16816(float (&d)[4], uint32_t a0, uint32_t a1, uint32_t a2, uint32_t a3, uint32_t b0, uint32_t b1) {
  asm volatile("mma.sync.aligned.m16n8k16.row.col.f32.bf16.bf16.f32 {%0,%1,%2,%3}, {%4,%5,%6,%7}, {%8,%9}, {%0,%1,%2,%3};"
               : "+f"(d[0]), "+f"(d[1]), "+f"(d[2]), "+f"(d[3]) : "r"(a0), "r"(a1), "r"(a2), "r"(a3), "r"(b0), "r"(b1));
}
__device__ __forceinline__ uint32_t movt(uint32_t a) { uint32_t d; asm volatile("movmatrix.sync.aligned.m8n8.trans.b16 %0, %1;" : "=r"(d) : "r"(a)); return d; }
__device__ __forceinline__ void att_exact(float (&O)[12], const uint32_t (&qa)[8], int h, int lane) {
  const uint32_t* kv = (const uint32_t*)qkv_block(32 + h, 0) + lane;
  float o0[4] = {0, 0, 0, 0}, o1[4] = {0, 0, 0, 0}, o2[4] = {0, 0, 0, 0};
  float m0 = -INFINITY, m1 = -INFINITY;
#pragma unroll 2
  for (int t = 0; t < 128; t++) {
    uint32_t k[6], v[6];
#pragma unroll
    for (int i = 0; i < 6; i++) {
      k[i] = __ldcg(kv + (t >> 3) * 3072 + (t & 7) * 192 + i * 32);
      v[i] = __ldcg(kv + (((t >> 3) + 1) & 15) * 3072 + 1536 + (t & 7) * 192 + i * 32);
    }
#pragma unroll
    for (int i = 0; i < 6; i++) {
      const uint32_t f = i >= 3 ? 0x63006300u : 0x3F803F80u;
      asm("mul.rn.bf16x2 %0, %0, %1;\n mul.rn.bf16x2 %0, %0, %1;" : "+r"(k[i]) : "r"(f));
    }
    float s0[4] = {0, 0, 0, 0}, s1[4] = {0, 0, 0, 0};
    mma16816(s0, qa[0], qa[1], qa[2], qa[3], k[0], k[1]); mma16816(s0, qa[4], qa[5], 0u, 0u, k[2], 0u);
    mma16816(s1, qa[0], qa[1], qa[2], qa[3], k[3], k[4]); mma16816(s1, qa[4], qa[5], 0u, 0u, k[5], 0u);
    float n0 = fmaxf(fmaxf(s0[0], s0[1]), fmaxf(s1[0], s1[1])), n1 = fmaxf(fmaxf(s0[2], s0[3]), fmaxf(s1[2], s1[3]));
    n0 = fmaxf(n0, __shfl_xor_sync(0xffffffffu, n0, 1)); n0 = fmaxf(n0, __shfl_xor_sync(0xffffffffu, n0, 2));
    n1 = fmaxf(n1, __shfl_xor_sync(0xffffffffu, n1, 1)); n1 = fmaxf(n1, __shfl_xor_sync(0xffffffffu, n1, 2));
    n0 = fmaxf(n0, m0); n1 = fmaxf(n1, m1);
    const float c0 = ex2(m0 - n0), c1 = ex2(m1 - n1);
    m0 = n0; m1 = n1;
    o0[0] *= c0; o0[1] *= c0; o0[2] *= c1; o0[3] *= c1;
    o1[0] *= c0; o1[1] *= c0; o1[2] *= c1; o1[3] *= c1;
    o2[0] *= c0; o2[1] *= c0; o2[2] *= c1; o2[3] *= c1;
    const uint32_t p0 = pack(ex2(s0[0] - n0), ex2(s0[1] - n0)), p1 = pack(ex2(s0[2] - n1), ex2(s0[3] - n1));
    const uint32_t p2 = pack(ex2(s1[0] - n0), ex2(s1[1] - n0)), p3 = pack(ex2(s1[2] - n1), ex2(s1[3] - n1));
    mma16816(o0, p0, p1, p2, p3, movt(v[0]), movt(v[3]));
    mma16816(o1, p0, p1, p2, p3, movt(v[1]), movt(v[4]));
    mma16816(o2, p0, p1, p2, p3, movt(v[2]), movt(v[5]));
  }
#pragma unroll
  for (int i = 0; i < 4; i++) { O[i] = o0[i]; O[4 + i] = o1[i]; O[8 + i] = o2[i]; }
}

constexpr uint32_t SMEM_BASE = 1024;
template <int U0, int U1> __device__ __forceinline__ void out_proj(float (&d0)[40], float (&d1)[40], uint32_t sb) {
  mbar_wait(sb + B_PFULL + 8 * (U0 % 3), (U0 / 3) & 1);
#pragma unroll
  for (int u = U0; u < U1; u++) {
    const uint32_t st = SMEM_BASE + ((4 - u % 3) & 3) * G_BYTES;
    const uint32_t al = dlo(st, 2048), bl = dlo(st + 20480, 5120);
    WG_FENCE();
#pragma unroll
    for (int k = 0; k < 5; k++) {
      wgmma_ss_n80<0, 1>(d0, desc2(al + 256 * k, 8), desc2(bl + 64 * k, HI_SW64), (u | k) != 0);
      wgmma_ss_n80<0, 1>(d1, desc2(al + 64 + 256 * k, 8), desc2(bl + 64 * k, HI_SW64), (u | k) != 0);
      if (k < 4) WG_DRAIN();
    }
    WG_COMMIT();
    const uint32_t nb = sb + B_PFULL + 8 * ((u + 1) % 3), np = ((u + 1) / 3) & 1;
    const uint32_t ok = u + 1 < U1 ? mbar_test(nb, np) : 1;
    WG_WAIT0();
    if (u < 3) mbar_arrive_elect(sb + B_PEMPTY + 8 * u);
    if (!ok) mbar_wait(nb, np);
  }
  fence_regs(d0); fence_regs(d1);
}

struct Maps { CUtensorMap x, w, wo, xb, seq[2], hid[2], out; const unsigned char *pwo, *pxb, *phid[2]; uint64_t dk[8][2], dv[8][4]; };
__device__ __forceinline__ void load_qkv(const Maps& mp, uint32_t sa, int i) {
  const uint32_t dst = sa + (i & 3) * QS_BYTES, bar = sa + OFF_BAR + B_QFULL + 8 * (i & 3), bar2 = bar + B_QF2;
  const int c = (CTA & 7) * 240;
  mbar_expect(bar, 32768);
  mbar_expect(bar2, 16384);
  tma2(dst, &mp.x, i * 64, (CTA >> 3) * 128, bar);
#pragma unroll
  for (int t = 0; t < 4; t++) tma2(dst + 16384 + t * 8192, &mp.w, c + t * 64, i * 64, t < 2 ? bar : bar2);
}
struct AttRegs { uint32_t qa[8], PA[16], PB[16]; float SA[32], SB[32], O[12]; };
__device__ __forceinline__ void issue_v(float (&O)[12], const uint32_t (&P)[16], const uint64_t* dv, int acc) {
#pragma unroll
  for (int c = 0; c < 4; c++) wgmma_rs_n24<1>(O, P[4 * c], P[4 * c + 1], P[4 * c + 2], P[4 * c + 3], dv[c], c ? 1 : acc);
}
__device__ __forceinline__ void issue_q(float (&S)[32], const uint32_t (&qa)[8], const uint64_t* dk) {
  wgmma_rs_n64<0>(S, qa[0], qa[1], qa[2], qa[3], dk[0], 0);
  wgmma_rs_n64<0>(S, qa[4], qa[5], qa[6], qa[7], dk[1], 1);
}
template <bool HEAD> __device__ __forceinline__ void att_group(AttRegs& a, const Maps& mp, uint32_t sb, uint32_t ph, int p, uint32_t half, uint32_t& ok1, uint32_t& failed) {
  uint32_t t = 0;
  if (HEAD) { t = tid_now(); load_q(a.qa, sb - OFF_BAR + OFF_Q + p * 6144 + (t >> 5) * 768 + (t & 31) * 4); }
#pragma unroll
  for (int s = 0; s < 4; s++) {
    if (HEAD && s == 1) {
      uint32_t v[6];
      const int q = (p - 1) & 3;
      WG_FENCE(); issue_q(a.SA, a.qa, mp.dk[2]); WG_COMMIT();
      const bool bad = norm_o(a.O, v, (t & 28) | (p & 1) * 2);
      fence_regs(v);
      WG_FENCE();
      issue_v(a.O, a.PA, mp.dv[2], 0); WG_COMMIT();
      store_o(v, q, t);
      failed |= (uint32_t)bad << q & 7;
      __syncwarp();
      asm volatile("{.reg .pred p, q; elect.sync _|p, 0xffffffff; setp.ne.and.u32 q, %1, 0, p; @q mbarrier.arrive.shared::cta.b64 _, [%0];}" ::"r"(sb + B_O + 8 * q), "r"(bad ? 0 : p) : "memory");
      softmax_tile<0xFF>(a.SB, a.PB, half);
    } else {
      softmax_tile<0x07>(a.SB, a.PB, half);
      WG_FENCE();
      att_issue(a.SA, a.PA, a.O, a.qa, mp.dk[2 * s], mp.dv[2 * s]);
      if (__builtin_expect(!ok1, 0)) touch<0xF8>(a.SB, a.qa[6]);
      softmax_tile<0xF8>(a.SB, a.PB, half);
    }
    fence_regs(a.PB);
    pin(a.PB, sb + 448, half);
    WG_WAIT0(); fence_regs(a.SA); fence_regs(a.O);
    const uint32_t kvb = sb + B_KVFULL + 8 * ((s + 1) & 3), kvp = s == 3 ? ph ^ 1 : ph;
    ok1 = mbar_test(kvb, kvp);
    if (HEAD && s == 0) {
      WG_FENCE(); issue_v(a.O, a.PB, mp.dv[1], 1); WG_COMMIT();
      const uint32_t mm = row_shift(fmaxf(fmaxf(a.SA[0], a.SA[1]), fmaxf(a.SA[8], a.SA[9])), fmaxf(fmaxf(a.SA[2], a.SA[3]), fmaxf(a.SA[10], a.SA[11])));
      const float m0 = __uint_as_float(mm << 16), m1 = __uint_as_float(mm & 0xffff0000u);
      if (((t + 2 * p) & 3) == 2) { a.qa[4] = mm & 0xffffu; a.qa[5] = mm >> 16; }
      fence_regs(a.qa);
      WG_FENCE();
      issue_q(a.SB, a.qa, mp.dk[1]); WG_COMMIT();
      if (__builtin_expect(!ok1, 0)) { mbar_wait(kvb, kvp); touch<0xFF>(a.SA, a.qa[6]); }
#pragma unroll
      for (int i = 0; i < 32; i++) a.SA[i] = fmaf((i & 2) ? m1 : m0, (i & 4) ? 0x1p-71f : 0x1p71f, a.SA[i]);
      softmax_tile<0xFF>(a.SA, a.PA, half);
    } else {
      softmax_tile<0x07>(a.SA, a.PA, half);
      WG_FENCE();
      att_issue(a.SB, a.PB, a.O, a.qa, mp.dk[2 * s + 1], mp.dv[2 * s + 1]);
      if (__builtin_expect(!ok1, 0)) { mbar_wait(kvb, kvp); touch<0xF8>(a.SA, a.qa[6]); }
      softmax_tile<0xF8>(a.SA, a.PA, half);
    }
    fence_regs(a.PA);
    pin(a.PA, sb + 448, half);
    WG_WAIT0(); fence_regs(a.SB); fence_regs(a.O);
    mbar_arrive_elect(sb + B_KVEMPTY + 8 * s);
  }
}

__global__ void __launch_bounds__(512, 1) fused_kernel(const __grid_constant__ Maps mp, __nv_bfloat16* __restrict__ out) {
  extern __shared__ __align__(1024) unsigned char smem_raw[];
  const uint32_t sa = ((uint32_t)__cvta_generic_to_shared(smem_raw) + 1023) & ~1023u;
  const uint32_t sb = sa + OFF_BAR;
  if ((sa & 0x3FFFF) != SMEM_BASE) return;
  const int wg = __shfl_sync(0xffffffffu, threadIdx.x >> 7, 0);
  const int warp = __shfl_sync(0xffffffffu, (threadIdx.x >> 5) & 3, 0);
  const int lane = threadIdx.x & 31;
  const int rb = CTA >> 3, j = CTA & 7, r2 = rb & 14;
  if (wg == 3 && warp == 0) {
#pragma unroll
    for (int i = 0; i < 4; i++) { mbar_init(sb + B_QFULL + 8 * i, 1); mbar_init(sb + B_QF2 + 8 * i, 1); }
    asm volatile("fence.mbarrier_init.release.cluster;\n fence.proxy.async.shared::cta;" ::: "memory");
    load_qkv(mp, sa, 0);
  }
  if (threadIdx.x == 0) {
    for (int i = 0; i < 4; i++) {
      mbar_init(sb + B_QEMPTY + 8 * i, 12);
      mbar_init(sb + B_GFULL + 8 * i, 1); mbar_init(sb + B_GEMPTY + 8 * i, 4);
      mbar_init(sb + B_KVFULL + 8 * i, 1); mbar_init(sb + B_KVEMPTY + 8 * i, 8);
      mbar_init(sb + B_O + 8 * i, i < 3 ? 8 : 1);
    }
    mbar_init(sb + B_Q, 1); mbar_init(sb + B_Q2, 1); mbar_init(sb + B_ST, 12); mbar_init(sb + B_ST2, 12); mbar_init(sb + B_STFREE, 1);
    mbar_init(sb + B_F1, 4); mbar_init(sb + B_F1A, 4); mbar_init(sb + B_F1FREE, 1); mbar_init(sb + B_X, 4); mbar_init(sb + B_X2, 1);
    for (int i = 0; i < 3; i++) { mbar_init(sb + B_PFULL + 8 * i, 1); mbar_init(sb + B_PEMPTY + 8 * i, 4); }
    asm volatile("st.shared.u64 [%0], %1;" ::"r"(sb + B_ZERO), "l"(0ull) : "memory");
    asm volatile("st.shared.u64 [%0], %1;" ::"r"(sb + B_CONST), "l"(0x3F003F00ull) : "memory");
    asm volatile("fence.mbarrier_init.release.cluster;" ::: "memory");
  }
  __syncthreads();
  if (wg == 3 && warp == 0) load_qkv(mp, sa, 1);
  if (wg == 3) {
    asm volatile("setmaxnreg.dec.sync.aligned.u32 24;");
    if (warp == 1) {
      const unsigned int* fl = g_cnt + C_Q0 + (lane == 16 ? j / 3 : ((lane < 16 ? 8 : 16) + j) / 3) * 16 + (lane == 16 ? rb : (lane - (lane > 16)) & 15);
      const unsigned char* kv = qkv_block(32 + 4 * j, 0);
      mbar_wait(sb + B_ST, 0);
      uint32_t ready = poll_flags(fl, 1, 0x10001u);
      mbar_expect(sb + B_Q, 6144);
      bulk(sa + OFF_Q, qkv_block(4 * j, rb), 6144, sb + B_Q);
      mbar_expect(sb + B_KVFULL, 6144);
      bulk(sa + OFF_KV, kv, 6144, sb + B_KVFULL);
#pragma unroll 1
      for (int i = 1; i < 16; i++) {
        const uint32_t s = i & 3;
        if (ready != 0xffffffffu) ready = poll_flags(fl, 1, 0x10001u << i);
        if (i >= 4) mbar_wait(sb + B_KVEMPTY + 8 * s, ((i >> 2) - 1) & 1);
        mbar_expect(sb + B_KVFULL + 8 * s, KV_BYTES);
        bulk(sa + OFF_KV + s * KV_BYTES, kv + i * KV_BYTES, KV_BYTES, sb + B_KVFULL + 8 * s);
      }
      poll_flags(g_cnt + C_QKV + (lane & 15), 8, 0xffffffffu);
      mbar_expect(sb + B_Q2, 3 * 6144);
      bulk(sa + OFF_Q + 6144, qkv_block(4 * j + 1, rb), 6144, sb + B_Q2);
      bulk(sa + OFF_Q + 2 * 6144, qkv_block(4 * j + 2, rb), 6144, sb + B_Q2);
      bulk(sa + OFF_Q + 3 * 6144, qkv_block(4 * j + 3, rb), 6144, sb + B_Q2);
#pragma unroll 1
      for (int p = 1; p < 5; p++) {
        mbar_wait(sb + B_KVEMPTY, 1);
        mbar_expect(sb + B_KVFULL, p < 4 ? KV_BYTES : 6144);
        bulk(sa + OFF_KV + 6144, kv + 6144, 6144, sb + B_KVFULL);
        if (p == 4) break;
        kv += 16 * KV_BYTES;
        bulk(sa + OFF_KV, kv, 6144, sb + B_KVFULL);
#pragma unroll 1
        for (int i = 1; i < 16; i++) {
          const uint32_t s = i & 3;
          mbar_wait(sb + B_KVEMPTY + 8 * s, ((i >> 2) - 1) & 1);
          mbar_expect(sb + B_KVFULL + 8 * s, KV_BYTES);
          bulk(sa + OFF_KV + s * KV_BYTES, kv + i * KV_BYTES, KV_BYTES, sb + B_KVFULL + 8 * s);
        }
      }
    } else if (warp == 0) {
#pragma unroll 1
      for (int i = 2; i < 10; i++) {
        const uint32_t s = i & 3;
        if (i >= 4) mbar_wait(sb + B_QEMPTY + 8 * s, ((i >> 2) - 1) & 1);
      load_qkv(mp, sa, i);
      }
      const int part = j >> 2, cb = j & 3;
#pragma unroll 1
      for (int g = 0; g < 10; g++) {
        const uint32_t s = g & 1, dst = sa + (3 - s) * G_BYTES, bar = sb + B_GFULL + 8 * s;
        if (g >= 2) mbar_wait(sb + B_GEMPTY + 8 * s, ((g >> 1) - 1) & 1);
        else if (g == 0) mbar_wait(sb + B_QEMPTY + 16, 1);
        else mbar_wait(sb + B_QEMPTY + 8, 0);
        if (g == 2) mbar_wait<200>(sb + B_KVFULL + 8, 0);
        mbar_expect(bar, G_BYTES);
        tma2(dst, &mp.xb, g * 64, rb * 128, bar);
        tma2(dst + 16384, &mp.hid[part], g * 64, cb * 160, bar);
      }
      mbar_wait(sb + B_STFREE, 0);
      uint32_t ready = 0;
#pragma unroll 1
      for (int g = 0; g < 32; g++) {
        const uint32_t s = (g + 2) & 3, dst = sa + (3 - s) * G_BYTES, bar = sb + B_GFULL + 8 * s;
        if (g >= 2) mbar_wait(sb + B_GEMPTY + 8 * s, ((g - 2) >> 2) & 1);
        if (g == 4) mbar_wait(sb + B_F1FREE, 0);
        if (g >= 2) mbar_wait(sb + B_GFULL + 8 * (g & 3), (g >> 2) & 1);
        mbar_expect(bar, g < 2 ? 16384 : G_BYTES);
        const int kk = ((g < 4 ? g ^ (rb & 1) * 2 : g) + 2 * r2) & 31;
        tma2(dst, &mp.seq[part], kk * 64, rb * 128, bar);
        if ((g & 3) == cb && g < 28)
          asm volatile(ONE("cp.async.bulk.prefetch.tensor.2d.L2.global [%0, {%1,%2}];") ::"l"(&mp.seq[part]), "r"(((g + 4 + 2 * r2) & 31) * 64), "r"(rb * 128) : "memory");
        if (g >= 2) {
          if (!((ready >> kk) & 1)) ready = poll_flags(g_cnt + C_F1 + j * 16 + (lane >> 1), 1, 1u << kk);
          bulk(dst + 16384, g_ab + ((size_t)j * 256 + kk * 8) * 2560, 20480, bar);
        }
      }
      const unsigned int* fo = g_cnt + C_O + rb * 8 + (lane & 3);
      ready = poll_flags(fo, 8, 3);
#pragma unroll 1
      for (int u = 0, s = 0, ph = 1; u < 6; u++) {
        const uint32_t dst = sa + ((4 - s) & 3) * G_BYTES, bar = sb + B_PFULL + 8 * s;
        if (u < 3) mbar_wait(sb + B_GEMPTY + 8 * ((u + 3) & 3), u == 0);
        else mbar_wait(sb + B_PEMPTY + 8 * s, ph);
        mbar_expect(bar, P_BYTES);
#pragma unroll
        for (int t = 0; t < 3; t++) tma3(dst + 20480 + t * 5120, &mp.wo, j * 80 + t * 32, (u >> 1) * 20, (u & 1) * 4, bar);
        if (u == 4 && !(ready & 4)) poll_flags(fo, 8, 4);
        bulk(dst, g_o + ((size_t)rb * 80 + u * 10) * 2048, 20480, bar);
        if (++s == 3) { s = 0; ph ^= 1; }
      }
      mbar_wait(sb + B_O + 24, 0);
      if (__any_sync(0xffffffffu, lane == 0 && atomicAdd(g_cnt + C_DONE, 1) == 127))
#pragma unroll
        for (int i = 0; i < C_NUM; i += 128) stg128(g_cnt + i + 4 * lane, 0, 0, 0, 0);
    } else if (warp == 3) {
      unsigned char *d0 = qkv_block(12 * j, rb), *d1 = qkv_block(12 * j + 4, rb), *d2 = qkv_block(12 * j + 8, rb);
      asm volatile("" : "+l"(d0), "+l"(d1), "+l"(d2));
      mbar_wait(sb + B_ST, 0);
      fence_smem();
      bulk_store(d0, sa + OFF_Q + 6144, 6144);
      bulk_store(d1, sa + OFF_Q + 2 * 6144, 6144);
      bulk_store(d2, sa + OFF_Q + 3 * 6144, 6144);
      asm volatile("cp.async.bulk.commit_group;\n cp.async.bulk.wait_group 0;" ::: "memory");
      fence_async(); cnt_add(C_Q0 + j * 16 + rb);
      mbar_wait(sb + B_ST2, 0);
      fence_smem();
#pragma unroll 1
      for (int l = 1, i = 1; l < 12; l++)
        if (l & 3) {
          mbar_wait<200>(sb + B_KVFULL + 8 * (i & 3), (i >> 2) & 1); i++;
          bulk_store(qkv_block(12 * j + l, rb), sa + l * 6144, 6144);
        }
      bulk_store(g_o3 + CTA * 320, sa, 5120);
      asm volatile("cp.async.bulk.commit_group;" ::: "memory");
      asm volatile("cp.async.bulk.wait_group.read 0;" ::: "memory");
      mbar_arrive_elect(sb + B_STFREE);
      asm volatile("cp.async.bulk.wait_group 0;" ::: "memory");
      fence_async(); cnt_add(C_QKV + rb);
      mbar_wait(sb + B_F1A, 0);
      fence_smem();
      bulk_store(g_ab + ((size_t)j * 256 + rb * 16) * 2560, sa + G_BYTES + 16384, 20480);
      mbar_wait(sb + B_F1, 0);
      bulk_store(g_ab + ((size_t)j * 256 + rb * 16 + 8) * 2560, sa + 16384, 20480);
      asm volatile("cp.async.bulk.commit_group;\n cp.async.bulk.wait_group 0;" ::: "memory");
      fence_async(); cnt_add(C_F1 + j * 16 + rb);
      mbar_arrive_elect(sb + B_F1FREE);
      mbar_wait(sb + B_X, 0);
      fence_smem();
      bulk_store(g_x + (size_t)CTA * 1280, sa + OFF_X, 20480);
      asm volatile("cp.async.bulk.commit_group;\n cp.async.bulk.wait_group 0;" ::: "memory");
      fence_async(); cnt_add(C_F2 + CTA);
      poll_flags(g_cnt + C_F2 + (CTA ^ 4), 1, 1);
      mbar_expect(sb + B_X2, 20480);
      bulk(sa + OFF_X, g_x + (size_t)(CTA ^ 4) * 1280, 20480, sb + B_X2);
    } else {
      mbar_wait(sb + B_QFULL, 0); mbar_wait(sb + B_QFULL, 1); mbar_wait(sb + B_QFULL, 0);
      asm volatile(ONE("cp.async.bulk.prefetch.L2.global [%0], 20480;") ::"l"(mp.pxb + CTA * 20480) : "memory");
      asm volatile(ONE("cp.async.bulk.prefetch.L2.global [%0], 12800;") ::"l"(mp.phid[CTA & 1] + (CTA >> 1) * 12800) : "memory");
      asm volatile(ONE("cp.async.bulk.prefetch.L2.global [%0], 6400;") ::"l"(mp.pwo + CTA * 6400) : "memory");
#pragma unroll 1
      for (int p = 0; p < 3; p++) { mbar_wait(sb + B_O + 8 * p, 0); asm volatile("fence.acq_rel.gpu;" ::: "memory"); cnt_add(C_O + rb * 8 + p); }
      mbar_expect(sb + B_Q, 30720);
#pragma unroll 1
      for (int t = 0; t < 6; t++) tma3(sa + OFF_Q + t * 5120, &mp.wo, j * 80 + (t % 3) * 32, 60, (t / 3) * 4, sb + B_Q);
      mbar_wait(sb + B_X2, 0);
      poll_flags<false>(g_cnt + C_O + rb * 8 + 3, 64, 1);
      mbar_arrive_elect(sb + B_O + 24);
    }
    __syncwarp();
  } else if (wg == 2) {
    asm volatile("setmaxnreg.inc.sync.aligned.u32 192;");
    {
      float d0[56], d1[56];
#pragma unroll 1
      for (int i = 0; i < 10; i++) {
        const uint32_t s = i & 3, st = sa + s * QS_BYTES;
        const uint32_t al = dlo(st, 16), bl = dlo(st + 32768, 8192);
        mbar_wait(sb + B_QFULL + 8 * s, (i >> 2) & 1);
        mbar_wait(sb + B_QF2 + 8 * s, (i >> 2) & 1);
        WG_FENCE();
#pragma unroll
        for (int k = 0; k < 4; k++) {
          wgmma_ss_n112<0, 1>(d0, desc2(al + 2 * k, HI_SW128), desc2(bl + 128 * k, HI_SW128), (i | k) != 0);
          wgmma_ss_n112<0, 1>(d1, desc2(al + 512 + 2 * k, HI_SW128), desc2(bl + 128 * k, HI_SW128), (i | k) != 0);
        }
        WG_COMMIT(); WG_WAIT0();
        mbar_arrive_elect(sb + B_QEMPTY + 8 * s);
      }
      fence_regs(d0); fence_regs(d1);
      store_qkv<16, 14, true>(d0, j, sa + warp * 768 + lane * 4, lane);
      store_qkv<16, 14, true>(d1, j, sa + 3072 + warp * 768 + lane * 4, lane);
      stage_done(sb + B_ST);
      mbar_wait(sb + B_QEMPTY, 0); mbar_wait(sb + B_QEMPTY + 8, 0);
      const int j2 = j + lds32(sb + B_ZERO);
      store_qkv<16, 14, false>(d0, j2, sa + warp * 768 + lane * 4, lane);
      store_qkv<16, 14, false>(d1, j2, sa + 3072 + warp * 768 + lane * 4, lane);
      sts128(sa + threadIdx.x * 16, ~0u, ~0u, ~0u, ~0u);
      stage_done(sb + B_ST2);
    }
    const int part = j >> 2, cb = j & 3;
    {
      float d0[80], d1[80];
      mbar_wait(sb + B_GFULL, 0);
#pragma unroll 1
      for (int gg = 0; gg < 5; gg++) {
#pragma unroll
        for (int s = 0; s < 2; s++) {
          const uint32_t al = dlo(SMEM_BASE + (3 - s) * G_BYTES, 16), bl = al + 1024;
          WG_FENCE();
#pragma unroll
          for (int k = 0; k < 4; k++) {
            wgmma_ss_n160<0, 0>(d0, desc2(al + 2 * k, HI_SW128), desc2(bl + 2 * k, HI_SW128), (gg | s | k) != 0);
            wgmma_ss_n160<0, 0>(d1, desc2(al + 512 + 2 * k, HI_SW128), desc2(bl + 2 * k, HI_SW128), (gg | s | k) != 0);
            if (k < 3) WG_DRAIN();
          }
          WG_COMMIT();
          const uint32_t ok = mbar_test(sb + B_GFULL + 8 * (s ^ 1), (gg + s) & 1);
          WG_WAIT0();
          mbar_arrive_elect(sb + B_GEMPTY + 8 * s);
          if (!ok && (s == 0 || gg < 4)) mbar_wait(sb + B_GFULL + 8 * (s ^ 1), (gg + s) & 1);
        }
      }
      fence_regs(d0); fence_regs(d1);
      {
        mbar_wait(sb + B_STFREE, 0);
        const uint32_t p = sa + 16384 + warp * 5120 + (lane >> 2) * 64 + ((lane ^ lane >> 3) & 3) * 16;
#pragma unroll
        for (int i = 0; i < 10; i++) {
          const int o = 8 * i - 6 * (i & 1);
          sts128(p + G_BYTES + (i & 1) * 2560 + (i >> 1) * 512, pack(d0[o], d0[o + 1]), pack(d0[o + 4], d0[o + 5]), pack(d0[o + 8], d0[o + 9]), pack(d0[o + 12], d0[o + 13]));
        }
        stage_done(sb + B_F1A);
#pragma unroll
        for (int i = 0; i < 10; i++) {
          const int o = 8 * i - 6 * (i & 1);
          sts128(p + (i & 1) * 2560 + (i >> 1) * 512, pack(d1[o], d1[o + 1]), pack(d1[o + 4], d1[o + 5]), pack(d1[o + 8], d1[o + 9]), pack(d1[o + 12], d1[o + 13]));
        }
        fence_smem();
        stage_done(sb + B_F1);
        mbar_wait(sb + B_F1, 0);
      }
      mbar_wait(sb + B_GFULL + 16, 0);
#pragma unroll 1
      for (int gg = 0; gg < 8; gg++) {
#pragma unroll
        for (int u = 0; u < 4; u++) {
          const uint32_t s = (u + 2) & 3, st = SMEM_BASE + (3 - s) * G_BYTES;
          const uint32_t a0 = dlo(st, 16) + part * 512, a1 = dlo(st, 16) + 512 - part * 512, bl = dlo(st + 16384, 512);
          WG_FENCE();
#pragma unroll
          for (int k = 0; k < 4; k++) {
            wgmma_ss_n160<0, 1>(d0, desc2(a0 + 2 * k, HI_SW128), desc2(bl + 320 * k, (2560 >> 4) | (2u << 30)), (gg | u | k) != 0);
            if (k == 1 && !(u & 1)) WG_DRAIN();
            wgmma_ss_n160<0, 1>(d1, desc2(a1 + 2 * k, HI_SW128), desc2(bl + 320 * k, (2560 >> 4) | (2u << 30)), (gg | u | k) != 0);
            if (k < 3) WG_DRAIN();
          }
          WG_COMMIT();
          const uint32_t nb = sb + B_GFULL + 8 * ((s + 1) & 3), np = (gg + (u >= 1)) & 1;
          const uint32_t ok = mbar_test(nb, np);
          WG_WAIT0();
          mbar_arrive_elect(sb + B_GEMPTY + 8 * s);
          if (!ok && (u < 3 || gg < 7)) mbar_wait(nb, np);
        }
      }
      fence_regs(d0); fence_regs(d1);
      const uint32_t xa = sa + OFF_X + (threadIdx.x & 127) * 16;
#pragma unroll
      for (int q = 0; q < 10; q++)
        sts128(xa + q * 2048, pack(d1[8 * q], d1[8 * q + 1]), pack(d1[8 * q + 2], d1[8 * q + 3]), pack(d1[8 * q + 4], d1[8 * q + 5]), pack(d1[8 * q + 6], d1[8 * q + 7]));
      stage_done(sb + B_X);
      float e0[40], e1[40];
      out_proj<0, 4>(e0, e1, sb);
      mbar_wait(sb + B_X2, 0);
      {
        const float sg = part ? -1.f : 1.f;
        __nv_bfloat16* op = out + (size_t)(rb * 128 + part * 64 + warp * 16 + (lane >> 2)) * 1280 + 640 + cb * 160 + (lane & 3) * 8;
#pragma unroll
        for (int q = 0; q < 5; q++) {
#pragma unroll
          for (int h2 = 0; h2 < 2; h2++) {
            uint32_t v[4];
            asm volatile("ld.shared.v4.u32 {%0,%1,%2,%3}, [%4];" : "=r"(v[0]), "=r"(v[1]), "=r"(v[2]), "=r"(v[3]) : "r"(xa + (2 * q + h2) * 2048) : "memory");
#pragma unroll
            for (int e = 0; e < 4; e++) {
              const int o = 16 * q + 8 * h2 + 2 * e;
              d0[o] = (d0[o] - __uint_as_float(v[e] << 16)) * sg;
              d0[o + 1] = (d0[o + 1] - __uint_as_float(v[e] & 0xffff0000u)) * sg;
            }
          }
#pragma unroll
          for (int hh = 0; hh < 2; hh++) {
            const int o = 16 * q + 2 * hh;
            stg128(op + hh * 8 * 1280 + q * 32, pack(d0[o], d0[o + 1]), pack(d0[o + 4], d0[o + 5]), pack(d0[o + 8], d0[o + 9]), pack(d0[o + 12], d0[o + 13]));
          }
        }
      }
      {
        uint32_t a0[40], a1[40];
        const uint4* src = g_o3 + rb * 2560 + (threadIdx.x & 127);
        asm volatile("" : "+l"(src));
        out_proj<4, 6>(e0, e1, sb);
        mbar_wait(sb + B_O + 24, 0);
        load_o3(a0, src); load_o3(a1, src + 1280);
        mbar_wait(sb + B_Q, 1);
        check_o3(a0, src);
        mma_o3(e0, e1, a0, dlo(SMEM_BASE + OFF_Q, 5120));
        check_o3(a1, src + 1280);
        mma_o3(e0, e1, a1, dlo(SMEM_BASE + OFF_Q + 15360, 5120));
        WG_WAIT0();
        fence_regs(e0); fence_regs(e1);
      }
      const uint32_t stg = sa + OFF_X + warp * 5120;
      const uint32_t ra = stg + (lane & 15) * 160 + (lane >> 4) * 2560;
#pragma unroll
      for (int b = 0; b < 10; b++)
        asm volatile("stmatrix.sync.aligned.m8n8.x4.shared.b16 [%0], {%1,%2,%3,%4};" ::"r"(ra + b * 16), "r"(pack(e0[4 * b], e0[4 * b + 1])),
                     "r"(pack(e0[4 * b + 2], e0[4 * b + 3])), "r"(pack(e1[4 * b], e1[4 * b + 1])), "r"(pack(e1[4 * b + 2], e1[4 * b + 3])) : "memory");
      asm volatile("fence.proxy.async.shared::cta;" ::: "memory");
      __syncwarp();
      if (lane < 2) {
        asm volatile("cp.async.bulk.tensor.2d.global.shared::cta.bulk_group [%0, {%2,%3}], [%1];" ::"l"(&mp.out), "r"(stg + lane * 2560), "r"(j * 80),
                     "r"(rb * 128 + lane * 64 + warp * 16) : "memory");
        asm volatile("cp.async.bulk.commit_group;\n cp.async.bulk.wait_group.read 0;" ::: "memory");
      }
    }
  } else {
    asm volatile("setmaxnreg.inc.sync.aligned.u32 144;");
    {
      float d[64];
#pragma unroll 1
      for (int i = 0; i < 10; i++) {
        const uint32_t s = i & 3, st = sa + s * QS_BYTES;
        const uint32_t al = dlo(st + wg * 8192, 16), bl = dlo(st + 16384, 8192);
        mbar_wait(sb + B_QFULL + 8 * s, (i >> 2) & 1);
        WG_FENCE();
#pragma unroll
        for (int k = 0; k < 4; k++) wgmma_ss_n128<0, 1>(d, desc2(al + 2 * k, HI_SW128), desc2(bl + 128 * k, HI_SW128), (i | k) != 0);
        WG_COMMIT(); WG_WAIT0();
        mbar_arrive_elect(sb + B_QEMPTY + 8 * s);
      }
      fence_regs(d);
      store_qkv<0, 16, true>(d, j, sa + wg * 3072 + warp * 768 + lane * 4, lane);
      stage_done(sb + B_ST);
      mbar_wait(sb + B_QEMPTY, 0); mbar_wait(sb + B_QEMPTY + 8, 0);
      store_qkv<0, 16, false>(d, j + lds32(sb + B_ZERO), sa + wg * 3072 + warp * 768 + lane * 4, lane);
      sts128(sa + threadIdx.x * 16, ~0u, ~0u, ~0u, ~0u);
      stage_done(sb + B_ST2);
    }
    AttRegs a;
    uint32_t (&qa)[8] = a.qa;
    float (&O)[12] = a.O;
    const uint32_t half = lds32(sb + B_CONST);
    uint32_t failed = 0, ok1 = half;
#pragma unroll
    for (int i = 0; i < 16; i++) a.PA[i] = 0;
#pragma unroll
    for (int i = 0; i < 32; i++) a.SB[i] = 0.f;
#pragma unroll
    for (int i = 0; i < 12; i++) O[i] = 0.f;
    fence_regs(O); fence_regs(a.SB);
    qa[6] = lds32(sb + B_ZERO); qa[7] = lds32(sb + B_ZERO + 4);
    mbar_wait(sb + B_KVFULL, 0);
#pragma unroll 1
    for (int p = 0; p < 4; p++) {
      mbar_wait(sb + (p ? B_Q2 : B_Q), 0);
      att_group<true>(a, mp, sb, 0, p, half, ok1, failed);
#pragma unroll 1
      for (int r = 1; r < 4; r++) att_group<false>(a, mp, sb, r & 1, p, half, ok1, failed);
    }
    WG_FENCE();
    issue_v(O, a.PA, mp.dv[0], 1);
    WG_COMMIT();
    softmax_tile<0xFF>(a.SB, a.PB, half);
    WG_FENCE();
    issue_v(O, a.PB, mp.dv[1], 1);
    WG_COMMIT(); WG_WAIT0(); fence_regs(O);
    cnt_add(C_O + rb * 8 + 3);
    const uint32_t t = tid_now();
    uint32_t v[6];
    if (norm_o(O, v, t & 28)) failed |= 8u;
    else store_o3(v, t);
    if (failed) {
#pragma unroll 1
      for (int p = 0; p < 4; p++)
        if (failed >> p & 1) {
          const uint32_t* qp = (const uint32_t*)qkv_block(4 * j + p, rb) + (t >> 5) * 192 + (t & 31);
#pragma unroll
          for (int i = 0; i < 6; i++) qa[i] = __ldcg(qp + (i & 1) * 96 + (i >> 1) * 32);
          if (((t >> 1) & 1) != (p & 1)) { qa[4] = 0; qa[5] = 0; }
          att_exact(O, qa, 4 * j + p, t & 31);
          norm_o(O, v, (t & 28) | (~p & 1) * 2);
          if (p == 3) store_o3(v, t);
          else { store_o(v, p, t); __syncwarp(); mbar_arrive_elect(sb + B_O + 8 * p); }
        }
    }
  }
}

typedef CUresult (*enc_fn)(CUtensorMap*, CUtensorMapDataType, cuuint32_t, void*, const cuuint64_t*, const cuuint64_t*, const cuuint32_t*,
                           const cuuint32_t*, CUtensorMapInterleave, CUtensorMapSwizzle, CUtensorMapL2promotion, CUtensorMapFloatOOBfill);
void make_map(enc_fn enc, CUtensorMap* m, void* p, uint64_t cols, uint64_t rows, uint32_t brows) {
  cuuint64_t gd[2] = {cols, rows}, gs[1] = {cols * 2};
  cuuint32_t bd[2] = {64, brows}, es[2] = {1, 1};
  enc(m, CU_TENSOR_MAP_DATA_TYPE_BFLOAT16, 2, p, gd, gs, bd, es, CU_TENSOR_MAP_INTERLEAVE_NONE, CU_TENSOR_MAP_SWIZZLE_128B,
      CU_TENSOR_MAP_L2_PROMOTION_L2_128B, CU_TENSOR_MAP_FLOAT_OOB_FILL_NONE);
}

}

extern "C" void kernel_launch(void* const* d_in, const int* in_sizes, int n_in, void* d_out, int out_size) {
  static enc_fn enc = nullptr;
  if (!enc) {
    void* fn = nullptr; cudaDriverEntryPointQueryResult qr;
    cudaGetDriverEntryPoint("cuTensorMapEncodeTiled", &fn, cudaEnableDefault, &qr);
    enc = (enc_fn)fn;
    cudaFuncSetAttribute(fused_kernel, cudaFuncAttributeMaxDynamicSharedMemorySize, SMEM_BYTES);
  }
  Maps mp;
  make_map(enc, &mp.x, d_in[0], D_, S_, 128);
  make_map(enc, &mp.w, d_in[1], 3 * D_, D_, 64);
  {
    cuuint64_t gd[3] = {D_, 80, 8}, gs[2] = {D_ * 2, D_ * 2 * 80};
    cuuint32_t bd[3] = {32, 20, 4}, es[3] = {1, 1, 1};
    enc(&mp.wo, CU_TENSOR_MAP_DATA_TYPE_BFLOAT16, 3, d_in[2], gd, gs, bd, es, CU_TENSOR_MAP_INTERLEAVE_NONE, CU_TENSOR_MAP_SWIZZLE_64B,
        CU_TENSOR_MAP_L2_PROMOTION_L2_128B, CU_TENSOR_MAP_FLOAT_OOB_FILL_NONE);
  }
  make_map(enc, &mp.xb, d_in[3], D_, S_, 128);
  make_map(enc, &mp.seq[0], d_in[4], S_, S_, 128);
  make_map(enc, &mp.seq[1], d_in[5], S_, S_, 128);
  make_map(enc, &mp.hid[0], d_in[6], D_, D_, 160);
  make_map(enc, &mp.hid[1], d_in[7], D_, D_, 160);
  {
    cuuint64_t gd[2] = {2 * D_, S_}, gs[1] = {4 * D_};
    cuuint32_t bd[2] = {80, 16}, es[2] = {1, 1};
    enc(&mp.out, CU_TENSOR_MAP_DATA_TYPE_BFLOAT16, 2, d_out, gd, gs, bd, es, CU_TENSOR_MAP_INTERLEAVE_NONE, CU_TENSOR_MAP_SWIZZLE_NONE,
        CU_TENSOR_MAP_L2_PROMOTION_NONE, CU_TENSOR_MAP_FLOAT_OOB_FILL_NONE);
  }
  for (int t = 0; t < 8; t++) {
    const uint64_t k = SMEM_BASE + OFF_KV + (t >> 1) * KV_BYTES + (t & 1) * 3072, v = k + 6144;
    mp.dk[t][0] = (k >> 4) | (8ull << 16) | (24ull << 32);
    mp.dk[t][1] = ((k + 256) >> 4) | (24ull << 32);
    for (int c = 0; c < 4; c++) mp.dv[t][c] = ((v + 768 * c) >> 4) | (24ull << 16) | (8ull << 32);
  }
  mp.pwo = (const unsigned char*)d_in[2];
  mp.pxb = (const unsigned char*)d_in[3]; mp.phid[0] = (const unsigned char*)d_in[6]; mp.phid[1] = (const unsigned char*)d_in[7];
  fused_kernel<<<128, 512, SMEM_BYTES, cudaStreamPerThread>>>(mp, (__nv_bfloat16*)d_out);
}
```
